```python
import torch

def _softmax(x, axis=-1):
    return torch.softmax(x, dim=axis)

def _gelu(x):
    return torch.nn.functional.gelu(x, approximate='tanh')

def _silu(x):
    return torch.nn.functional.silu(x)

def _sigmoid(x):
    return torch.sigmoid(x)

def _layernorm(x, axis=-1, eps=1e-05):
    m = x.mean(dim=axis, keepdim=True)
    v = x.var(dim=axis, keepdim=True, unbiased=False)
    return (x - m) / torch.sqrt(v + eps)

def _scatter_add(tgt, idx, src, axis=0):
    return tgt.clone().index_add_(axis, idx, src)

def _segment_sum(src, seg, n):
    out = torch.zeros((n,) + src.shape[1:], dtype=src.dtype)
    return out.index_add_(0, seg, src)

def _pad(x, pw):
    flat = tuple((v for pair in reversed(pw) for v in pair))
    return torch.nn.functional.pad(x, flat)
kernel_name = 'standalone__tree_speculative_verify_tree_attention_over_candidate_token_tree__decode'

def setup_inputs():

    _w = lambda a: (lambda t: t.to(torch.bfloat16) if t.is_floating_point() else t)(torch.as_tensor(a))
    B, Hq, Hkv, T, C, D = (2, 32, 16, 1, 4096, 128)
    tree_mask = torch.zeros((B, T, T), dtype=float)
    for b in range(B):
        parent = torch.zeros(T, dtype=torch.int64)
        for i in range(1, T):
            parent[i] = int(torch.randint(0, i, (1,)).item())
        for i in range(T):
            j = i
            tree_mask[b, i, j] = 1.0
            while j > 0:
                j = parent[j]
                tree_mask[b, i, j] = 1.0
    return {'q': _w((lambda *s: torch.randn(*s, dtype=torch.bfloat16) * 0.8)(B, Hq, T, D)), 'k_cache': _w((lambda *s: torch.randn(*s, dtype=torch.bfloat16) * 0.8)(B, Hkv, C, D)), 'v_cache': _w((lambda *s: torch.randn(*s, dtype=torch.bfloat16) * 0.05)(B, Hkv, C, D)), 'k_tree': _w((lambda *s: torch.randn(*s, dtype=torch.bfloat16) * 0.8)(B, Hkv, T, D)), 'v_tree': _w((lambda *s: torch.randn(*s, dtype=torch.bfloat16) * 0.05)(B, Hkv, T, D)), 'tree_mask': _w(tree_mask)}

def reference(q, k_cache, v_cache, k_tree, v_tree, tree_mask):
    B, Hq, T, D = q.shape
    Hkv, C = (k_cache.shape[1], k_cache.shape[2])
    rep = Hq // Hkv
    kc = (lambda x, n, axis: torch.repeat_interleave(x, n, dim=axis))(k_cache, rep, axis=1)
    vc = (lambda x, n, axis: torch.repeat_interleave(x, n, dim=axis))(v_cache, rep, axis=1)
    kt = (lambda x, n, axis: torch.repeat_interleave(x, n, dim=axis))(k_tree, rep, axis=1)
    vt = (lambda x, n, axis: torch.repeat_interleave(x, n, dim=axis))(v_tree, rep, axis=1)
    k = torch.concatenate([kc, kt], axis=2)
    v = torch.concatenate([vc, vt], axis=2)
    scale = D ** (-0.5)
    scores = torch.einsum('bhqd,bhkd->bhqk', q, k) * scale
    ctx_mask = torch.ones((B, 1, T, C), dtype=scores.dtype)
    tm = tree_mask[:, None, :, :].clone()
    full_mask = torch.concatenate([ctx_mask, tm], axis=-1)
    scores = scores + (1.0 - full_mask) * -1000000000.0
    p = _softmax(scores, axis=-1)
    return torch.einsum('bhqk,bhkd->bhqd', p, v)
```

```cpp
#include <cuda_runtime.h>
#include <cuda_bf16.h>
#include <stdint.h>

namespace {
constexpr int B_ = 2, HQ = 32, HKV = 16, CTX = 4096, D = 128;
constexpr int NPAIR = B_ * HKV;
constexpr int CPP = 4;
constexpr int KT = 16;
constexpr int TILE_BYTES = KT * D * 2;
constexpr int PART_WORDS = 264;

__device__ unsigned g_part[NPAIR * (CPP - 1) * PART_WORDS];

__device__ __forceinline__ uint32_t smem_u32(const void* p) { return (uint32_t)__cvta_generic_to_shared(p); }
__device__ __forceinline__ void cp16(uint32_t dst, const void* src) { asm volatile("cp.async.cg.shared.global [%0], [%1], 16;" :: "r"(dst), "l"(src) : "memory"); }
__device__ __forceinline__ void cp_commit() { asm volatile("cp.async.commit_group;" ::: "memory"); }
template<int N> __device__ __forceinline__ void cp_wait() { asm volatile("cp.async.wait_group %0;" :: "n"(N) : "memory"); }
__device__ __forceinline__ void ldsm4(uint32_t& r0, uint32_t& r1, uint32_t& r2, uint32_t& r3, uint32_t a) {
    asm volatile("ldmatrix.sync.aligned.m8n8.x4.shared.b16 {%0,%1,%2,%3}, [%4];" : "=r"(r0), "=r"(r1), "=r"(r2), "=r"(r3) : "r"(a) : "memory");
}
__device__ __forceinline__ void ldsm4t(uint32_t& r0, uint32_t& r1, uint32_t& r2, uint32_t& r3, uint32_t a) {
    asm volatile("ldmatrix.sync.aligned.m8n8.x4.trans.shared.b16 {%0,%1,%2,%3}, [%4];" : "=r"(r0), "=r"(r1), "=r"(r2), "=r"(r3) : "r"(a) : "memory");
}
__device__ __forceinline__ void mma16816(float (&c)[4], uint32_t a0, uint32_t a1, uint32_t a2, uint32_t a3, uint32_t b0, uint32_t b1) {
    asm volatile("mma.sync.aligned.m16n8k16.row.col.f32.bf16.bf16.f32 {%0,%1,%2,%3}, {%4,%5,%6,%7}, {%8,%9}, {%0,%1,%2,%3};"
        : "+f"(c[0]), "+f"(c[1]), "+f"(c[2]), "+f"(c[3]) : "r"(a0), "r"(a1), "r"(a2), "r"(a3), "r"(b0), "r"(b1));
}
__device__ __forceinline__ uint32_t movm_t(uint32_t a) { uint32_t d; asm volatile("movmatrix.sync.aligned.m8n8.trans.b16 %0, %1;" : "=r"(d) : "r"(a)); return d; }
__device__ __forceinline__ uint32_t pack_bf16(float lo, float hi) { uint32_t d; asm("cvt.rn.bf16x2.f32 %0, %1, %2;" : "=r"(d) : "f"(hi), "f"(lo)); return d; }
__device__ __forceinline__ float ex2(float x) { float y; asm("ex2.approx.ftz.f32 %0, %1;" : "=f"(y) : "f"(x)); return y; }
__device__ __forceinline__ unsigned enc(float x) { unsigned b = __float_as_uint(x); b = (b == 0xFFFFFFFFu) ? 0x7FFFFFFFu : b; return ~b; }
__device__ __forceinline__ float dec(unsigned u) { return __uint_as_float(~u); }
__device__ __forceinline__ unsigned ld_relaxed(const unsigned* p) { unsigned v; asm volatile("ld.relaxed.gpu.global.u32 %0, [%1];" : "=r"(v) : "l"(p) : "memory"); return v; }
__device__ __forceinline__ void st_relaxed(unsigned* p, unsigned v) { asm volatile("st.relaxed.gpu.global.u32 [%0], %1;" :: "l"(p), "r"(v) : "memory"); }

template<int W, int S>
struct Cfg {
    static constexpr int THREADS = W * 32;
    static constexpr int RING_BYTES = S * 2 * TILE_BYTES;
    static constexpr int Q_OFF = W * RING_BYTES;
    static constexpr int O_OFF = Q_OFF + W * 512;
    static constexpr int ML_OFF = O_OFF + W * 1024;
    static constexpr int TR_OFF = ML_OFF + W * 16;
    static constexpr int SMEM = TR_OFF + 16;
};

template<int W, int S, int HELP_TILES>
__global__ void __launch_bounds__(W * 32, 1)
attn_kernel(const __nv_bfloat16* __restrict__ Q, const __nv_bfloat16* __restrict__ K, const __nv_bfloat16* __restrict__ V,
            const __nv_bfloat16* __restrict__ Kt, const __nv_bfloat16* __restrict__ Vt, const __nv_bfloat16* __restrict__ Mask,
            __nv_bfloat16* __restrict__ Out)
{
    using C = Cfg<W, S>;
    extern __shared__ __align__(1024) char smem[];
    const int tid = threadIdx.x, warp = tid >> 5, lane = tid & 31;
    const int pair = blockIdx.x >> 2, q = blockIdx.x & 3;
    constexpr int OWN_TILES = CTX / KT - 3 * HELP_TILES;
    const int ntiles = (q == 3) ? OWN_TILES : HELP_TILES;
    const uint32_t sbase = smem_u32(smem);

    const size_t goff = (size_t)pair * (CTX * D * 2) + (size_t)(q * HELP_TILES + warp) * TILE_BYTES + lane * 16;
    const char* kp = (const char*)K + goff;
    const char* vp = (const char*)V + goff;
    const uint32_t ring = sbase + warp * C::RING_BYTES;
    const int hi = lane >> 4;
    const uint32_t x0 = hi * 256 + (((lane & 15) ^ hi) << 4);
    const uint32_t qs = sbase + C::Q_OFF + warp * 512;
    cp16(qs + lane * 16, (const char*)Q + (size_t)pair * 512 + lane * 16);
    auto issue = [&](uint32_t slot, const char* src) {
#pragma unroll
        for (int j = 0; j < 8; j++) cp16(slot + j * 512 + (x0 ^ (((2 * j) & 7) << 4)), src + j * 512);
    };
    constexpr size_t TSTEP = (size_t)W * TILE_BYTES;
#pragma unroll
    for (int s = 0; s < S; s++) {
        if (warp + s * W < ntiles) issue(ring + s * 2 * TILE_BYTES, kp + s * TSTEP);
        cp_commit();
        if (warp + s * W < ntiles) issue(ring + s * 2 * TILE_BYTES + TILE_BYTES, vp + s * TSTEP);
        cp_commit();
    }

    float vtree = 0.f;
    if (q == 3) {
        const int d = tid & 127;
        if (W * 32 >= 256 ? (tid < 256) : true) vtree = __bfloat162float(Vt[pair * D + d]);
        if (warp == 0) {
            uint4 qv = *(const uint4*)((const char*)Q + (size_t)pair * 512 + lane * 16);
            uint4 kv = *(const uint4*)((const char*)Kt + (size_t)pair * 256 + (lane & 15) * 16);
            const uint32_t* qa = (const uint32_t*)&qv; const uint32_t* ka = (const uint32_t*)&kv;
            float acc = 0.f;
#pragma unroll
            for (int i = 0; i < 4; i++) {
                acc += __uint_as_float(qa[i] << 16) * __uint_as_float(ka[i] << 16);
                acc += __uint_as_float(qa[i] & 0xffff0000u) * __uint_as_float(ka[i] & 0xffff0000u);
            }
#pragma unroll
            for (int o = 8; o >= 1; o >>= 1) acc += __shfl_xor_sync(0xffffffffu, acc, o);
            const float mk = __bfloat162float(Mask[pair / HKV]);
            const float st = (acc * 0.08838834764831845f + (1.0f - mk) * (-1000000000.0f)) * 1.4426950408889634f;
            if ((lane & 15) == 0) ((float*)(smem + C::TR_OFF))[hi] = st;
        }
    }

    uint32_t qf[8][2];
    cp_wait<2 * S - 1 + 0>();
    __syncwarp();
    {
        const uint32_t qa = qs + (lane & 1) * 256 + (lane >> 3) * 16;
#pragma unroll
        for (int j = 0; j < 4; j++) ldsm4(qf[2 * j][0], qf[2 * j][1], qf[2 * j + 1][0], qf[2 * j + 1][1], qa + j * 64);
    }

    const int r7 = lane & 7;
    const uint32_t ka_off = ((lane & 7) + ((lane >> 3) & 1) * 8) * 256 + ((((lane >> 4)) ^ r7) << 4);
    const uint32_t va_off = ((lane & 7) + (lane >> 4) * 8) * 256 + (((((lane >> 3) & 1)) ^ r7) << 4);

    float o[8][4];
#pragma unroll
    for (int i = 0; i < 8; i++) { o[i][0] = o[i][1] = o[i][2] = o[i][3] = 0.f; }
    float m0 = -INFINITY, m1 = -INFINITY, l0 = 0.f, l1 = 0.f;
    constexpr float SC = 0.08838834764831845f * 1.4426950408889634f;

    int slot = 0;
    const char* kn = kp + S * TSTEP;
    const char* vn = vp + S * TSTEP;
#pragma unroll 1
    for (int t = warp; t < ntiles; t += W) {
        const uint32_t ks = ring + slot * 2 * TILE_BYTES, vs = ks + TILE_BYTES;
        const bool more = (t + S * W) < ntiles;
        cp_wait<2 * S - 1>();
        __syncwarp();
        float sa[4] = {0.f, 0.f, 0.f, 0.f}, sb[4] = {0.f, 0.f, 0.f, 0.f};
#pragma unroll
        for (int k = 0; k < 8; k += 2) {
            uint32_t a0, a1, a2, a3, b0, b1, b2, b3;
            ldsm4(a0, a1, a2, a3, (ks + ka_off) ^ (k << 5));
            ldsm4(b0, b1, b2, b3, (ks + ka_off) ^ ((k + 1) << 5));
            mma16816(sa, a0, a1, a2, a3, qf[k][0], qf[k][1]);
            mma16816(sb, b0, b1, b2, b3, qf[k + 1][0], qf[k + 1][1]);
        }
        if (more) issue(ks, kn);
        cp_commit();
        kn += TSTEP;
        const float s0 = (sa[0] + sb[0]) * SC, s1 = (sa[1] + sb[1]) * SC, s2 = (sa[2] + sb[2]) * SC, s3 = (sa[3] + sb[3]) * SC;
        float x0m = fmaxf(s0, s2), x1m = fmaxf(s1, s3);
#pragma unroll
        for (int ofs = 4; ofs <= 16; ofs <<= 1) {
            x0m = fmaxf(x0m, __shfl_xor_sync(0xffffffffu, x0m, ofs));
            x1m = fmaxf(x1m, __shfl_xor_sync(0xffffffffu, x1m, ofs));
        }
        const float n0 = fmaxf(m0, x0m), n1 = fmaxf(m1, x1m);
        if (n0 != m0 || n1 != m1) {
            const float al0 = ex2(m0 - n0), al1 = ex2(m1 - n1);
            l0 *= al0; l1 *= al1;
#pragma unroll
            for (int i = 0; i < 8; i++) { o[i][0] *= al0; o[i][1] *= al1; o[i][2] *= al0; o[i][3] *= al1; }
            m0 = n0; m1 = n1;
        }
        const float p0 = ex2(s0 - m0), p1 = ex2(s1 - m1), p2 = ex2(s2 - m0), p3 = ex2(s3 - m1);
        l0 += p0 + p2; l1 += p1 + p3;
        const uint32_t pb0 = movm_t(pack_bf16(p0, p1)), pb1 = movm_t(pack_bf16(p2, p3));
        cp_wait<2 * S - 1>();
        __syncwarp();
#pragma unroll
        for (int mt = 0; mt < 8; mt++) {
            uint32_t a0, a1, a2, a3;
            ldsm4t(a0, a1, a2, a3, (vs + va_off) ^ (mt << 5));
            mma16816(o[mt], a0, a1, a2, a3, pb0, pb1);
        }
        if (more) issue(vs, vn);
        cp_commit();
        vn += TSTEP;
        slot = (slot + 1 == S) ? 0 : slot + 1;
    }

#pragma unroll
    for (int ofs = 4; ofs <= 16; ofs <<= 1) {
        l0 += __shfl_xor_sync(0xffffffffu, l0, ofs);
        l1 += __shfl_xor_sync(0xffffffffu, l1, ofs);
    }
    {
        float* so = (float*)(smem + C::O_OFF) + warp * 256;
        const int g = lane >> 2, tq = lane & 3;
#pragma unroll
        for (int mt = 0; mt < 8; mt++) {
            if ((mt >> 1) == tq) {
                so[mt * 16 + g] = o[mt][0]; so[128 + mt * 16 + g] = o[mt][1];
                so[mt * 16 + 8 + g] = o[mt][2]; so[128 + mt * 16 + 8 + g] = o[mt][3];
            }
        }
        if (lane == 0) *(float4*)(smem + C::ML_OFF + warp * 16) = make_float4(m0, m1, l0, l1);
    }
    __syncthreads();
    constexpr int OUTS_PER_THREAD = 256 / (W * 32) > 0 ? 256 / (W * 32) : 1;
    unsigned* part = g_part + pair * (CPP - 1) * PART_WORDS;
#pragma unroll
    for (int u = 0; u < OUTS_PER_THREAD; u++) {
        const int i = tid + u * W * 32;
        if (i < 256) {
            const int h = i >> 7;
            const float* ml = (const float*)(smem + C::ML_OFF);
            float M = -INFINITY;
#pragma unroll
            for (int w = 0; w < W; w++) M = fmaxf(M, ml[w * 4 + h]);
            float acc = 0.f, L = 0.f;
#pragma unroll
            for (int w = 0; w < W; w++) {
                const float mw = ml[w * 4 + h];
                const float e = (mw == -INFINITY) ? 0.f : ex2(mw - M);
                acc += e * ((const float*)(smem + C::O_OFF))[w * 256 + i];
                L += e * ml[w * 4 + 2 + h];
            }
            if (q != 3) {
                unsigned* dst = part + q * PART_WORDS;
                st_relaxed(dst + i, enc(acc));
                if ((i & 127) == 0) { st_relaxed(dst + 256 + h, enc(M)); st_relaxed(dst + 258 + h, enc(L)); }
            } else {
                unsigned ro[3], rm[3], rl[3];
                int guard = 0;
                while (true) {
#pragma unroll
                    for (int j = 0; j < 3; j++) {
                        ro[j] = ld_relaxed(part + j * PART_WORDS + i);
                        rm[j] = ld_relaxed(part + j * PART_WORDS + 256 + h);
                        rl[j] = ld_relaxed(part + j * PART_WORDS + 258 + h);
                    }
                    bool ok = true;
#pragma unroll
                    for (int j = 0; j < 3; j++) ok = ok && ro[j] && rm[j] && rl[j];
                    if (ok || ++guard > (1 << 22)) break;
                }
                const float st = ((const float*)(smem + C::TR_OFF))[h];
                float Mx = fmaxf(M, st);
#pragma unroll
                for (int j = 0; j < 3; j++) Mx = fmaxf(Mx, dec(rm[j]));
                const float e0 = ex2(M - Mx), et = ex2(st - Mx);
                float num = acc * e0 + et * vtree, den = L * e0 + et;
#pragma unroll
                for (int j = 0; j < 3; j++) { const float e = ex2(dec(rm[j]) - Mx); num += e * dec(ro[j]); den += e * dec(rl[j]); }
                Out[pair * 256 + i] = __float2bfloat16(num / den);
            }
        }
    }
    if (q == 3) {
        __syncthreads();
        for (int i = tid; i < 3 * PART_WORDS; i += W * 32) st_relaxed(part + i, 0u);
    }
}

template<int W, int S, int HELP_TILES>
inline void launch(const void* Q, const void* K, const void* V, const void* Kt, const void* Vt, const void* Mask, void* Out, cudaStream_t s) {
    auto kern = attn_kernel<W, S, HELP_TILES>;
    static bool init = false;
    if (!init) { cudaFuncSetAttribute(kern, cudaFuncAttributeMaxDynamicSharedMemorySize, Cfg<W, S>::SMEM); init = true; }
    kern<<<NPAIR * CPP, W * 32, Cfg<W, S>::SMEM, s>>>((const __nv_bfloat16*)Q, (const __nv_bfloat16*)K, (const __nv_bfloat16*)V,
        (const __nv_bfloat16*)Kt, (const __nv_bfloat16*)Vt, (const __nv_bfloat16*)Mask, (__nv_bfloat16*)Out);
}
}

extern "C" void kernel_launch(void* const* d_in, const int* in_sizes, int n_in, void* d_out, int out_size) {
    (void)in_sizes; (void)n_in; (void)out_size;
    launch<8, 2, 64>(d_in[0], d_in[1], d_in[2], d_in[3], d_in[4], d_in[5], d_out, cudaStreamPerThread);
}
```

```cpp
#include <cuda_runtime.h>
#include <cuda_bf16.h>
#include <stdint.h>

namespace {
constexpr int B_ = 2, HQ = 32, HKV = 16, CTX = 4096, D = 128;
constexpr int NPAIR = B_ * HKV;
constexpr int CPP = 4;
constexpr int KT = 16;
constexpr int TILE_BYTES = KT * D * 2;
constexpr int W = 8;

struct Scratch { uint2 part[NPAIR][CPP - 1][256]; unsigned ready[NPAIR][32]; };
__device__ Scratch g_scr;

__device__ __forceinline__ uint32_t smem_u32(const void* p) { return (uint32_t)__cvta_generic_to_shared(p); }
__device__ __forceinline__ void cp16(uint32_t dst, const void* src) { asm volatile("cp.async.cg.shared.global [%0], [%1], 16;" :: "r"(dst), "l"(src) : "memory"); }
__device__ __forceinline__ void cp16h(uint32_t dst, const void* src, uint64_t pol) { asm volatile("cp.async.cg.shared.global.L2::cache_hint [%0], [%1], 16, %2;" :: "r"(dst), "l"(src), "l"(pol) : "memory"); }
__device__ __forceinline__ void cp4(uint32_t dst, const void* src) { asm volatile("cp.async.ca.shared.global [%0], [%1], 4;" :: "r"(dst), "l"(src) : "memory"); }
__device__ __forceinline__ void cp_commit() { asm volatile("cp.async.commit_group;" ::: "memory"); }
template<int N> __device__ __forceinline__ void cp_wait() { asm volatile("cp.async.wait_group %0;" :: "n"(N) : "memory"); }
__device__ __forceinline__ void ldsm4(uint32_t& r0, uint32_t& r1, uint32_t& r2, uint32_t& r3, uint32_t a) {
    asm volatile("ldmatrix.sync.aligned.m8n8.x4.shared.b16 {%0,%1,%2,%3}, [%4];" : "=r"(r0), "=r"(r1), "=r"(r2), "=r"(r3) : "r"(a) : "memory");
}
__device__ __forceinline__ void ldsm4t(uint32_t& r0, uint32_t& r1, uint32_t& r2, uint32_t& r3, uint32_t a) {
    asm volatile("ldmatrix.sync.aligned.m8n8.x4.trans.shared.b16 {%0,%1,%2,%3}, [%4];" : "=r"(r0), "=r"(r1), "=r"(r2), "=r"(r3) : "r"(a) : "memory");
}
__device__ __forceinline__ void mma16816(float (&c)[4], uint32_t a0, uint32_t a1, uint32_t a2, uint32_t a3, uint32_t b0, uint32_t b1) {
    asm volatile("mma.sync.aligned.m16n8k16.row.col.f32.bf16.bf16.f32 {%0,%1,%2,%3}, {%4,%5,%6,%7}, {%8,%9}, {%0,%1,%2,%3};"
        : "+f"(c[0]), "+f"(c[1]), "+f"(c[2]), "+f"(c[3]) : "r"(a0), "r"(a1), "r"(a2), "r"(a3), "r"(b0), "r"(b1));
}
__device__ __forceinline__ uint32_t movm_t(uint32_t a) { uint32_t d; asm volatile("movmatrix.sync.aligned.m8n8.trans.b16 %0, %1;" : "=r"(d) : "r"(a)); return d; }
__device__ __forceinline__ uint32_t pack_bf16(float lo, float hi) { uint32_t d; asm("cvt.rn.bf16x2.f32 %0, %1, %2;" : "=r"(d) : "f"(hi), "f"(lo)); return d; }
__device__ __forceinline__ float ex2(float x) { float y; asm("ex2.approx.ftz.f32 %0, %1;" : "=f"(y) : "f"(x)); return y; }
__device__ __forceinline__ float lg2(float x) { float y; asm("lg2.approx.ftz.f32 %0, %1;" : "=f"(y) : "f"(x)); return y; }
__device__ __forceinline__ float rcp(float x) { float y; asm("rcp.approx.ftz.f32 %0, %1;" : "=f"(y) : "f"(x)); return y; }
__device__ __forceinline__ unsigned enc(float x) { unsigned b = __float_as_uint(x); b = (b == 0xFFFFFFFFu) ? 0x7FFFFFFFu : b; return ~b; }
__device__ __forceinline__ float dec(unsigned u) { return __uint_as_float(~u); }
__device__ __forceinline__ void ld_relaxed2_p(uint2& v, const uint2* p, unsigned pred) {
    asm volatile("{\n.reg .pred p;\nsetp.ne.u32 p, %3, 0;\n@p ld.relaxed.gpu.global.v2.u32 {%0,%1}, [%2];\n}" : "+r"(v.x), "+r"(v.y) : "l"(p), "r"(pred) : "memory");
}
__device__ __forceinline__ void st_relaxed2_p(uint2* p, unsigned a, unsigned b, unsigned pred) {
    asm volatile("{\n.reg .pred p;\nsetp.ne.u32 p, %3, 0;\n@p st.relaxed.gpu.global.v2.u32 [%0], {%1,%2};\n}" :: "l"(p), "r"(a), "r"(b), "r"(pred) : "memory");
}
__device__ __forceinline__ void st_relaxed1_p(unsigned* p, unsigned a, unsigned pred) {
    asm volatile("{\n.reg .pred p;\nsetp.ne.u32 p, %2, 0;\n@p st.relaxed.gpu.global.u32 [%0], %1;\n}" :: "l"(p), "r"(a), "r"(pred) : "memory");
}
__device__ __forceinline__ void st_b16_p(void* p, unsigned short v, unsigned pred) {
    asm volatile("{\n.reg .pred p;\nsetp.ne.u32 p, %2, 0;\n@p st.global.b16 [%0], %1;\n}" :: "l"(p), "h"(v), "r"(pred) : "memory");
}
__device__ __forceinline__ void sts4_p(uint32_t a, float x, float y, float z, float w, unsigned pred) {
    asm volatile("{\n.reg .pred p;\nsetp.ne.u32 p, %5, 0;\n@p st.shared.v4.f32 [%0], {%1,%2,%3,%4};\n}" :: "r"(a), "f"(x), "f"(y), "f"(z), "f"(w), "r"(pred) : "memory");
}
__device__ __forceinline__ void sts1_p(uint32_t a, float x, unsigned pred) {
    asm volatile("{\n.reg .pred p;\nsetp.ne.u32 p, %2, 0;\n@p st.shared.f32 [%0], %1;\n}" :: "r"(a), "f"(x), "r"(pred) : "memory");
}
__device__ __forceinline__ void bar_sync_p(int id, unsigned count, unsigned pred) {
    asm volatile("{\n.reg .pred p;\nsetp.ne.u32 p, %2, 0;\n@p barrier.cta.sync.aligned %0, %1;\n}" :: "r"(id), "r"(count), "r"(pred) : "memory");
}
__device__ __forceinline__ void bar_arrive(int id, unsigned count) { asm volatile("barrier.cta.arrive.aligned %0, %1;" :: "r"(id), "r"(count) : "memory"); }
__device__ __forceinline__ unsigned gtime32() { unsigned t; asm volatile("mov.u32 %0, %clock;" : "=r"(t) :: "memory"); return t; }

template<int S>
struct Cfg {
    static constexpr int THREADS = W * 32 + 32;
    static constexpr int RING_BYTES = S * 2 * TILE_BYTES;
    static constexpr int Q_OFF = W * RING_BYTES;
    static constexpr int TR_OFF = Q_OFF + W * 512;
    static constexpr int O_OFF = TR_OFF + 528;
    static constexpr int ML_OFF = O_OFF + W * 1024;
    static constexpr int SMEM = ML_OFF + 4 * W * 4;
};

template<int S, int HELP_TILES, int WARM, int PROF, int EARLY, int DELAY, int EF>
__global__ void __launch_bounds__(W * 32 + 32, 1)
attn_kernel(const __nv_bfloat16* __restrict__ Q, const __nv_bfloat16* __restrict__ K, const __nv_bfloat16* __restrict__ V,
            const __nv_bfloat16* __restrict__ Kt, const __nv_bfloat16* __restrict__ Vt, const __nv_bfloat16* __restrict__ Mask,
            __nv_bfloat16* __restrict__ Out, Scratch* __restrict__ scr)
{
    using C = Cfg<S>;
    static_assert(HELP_TILES >= S * W, "prologue assumes full ring");
    extern __shared__ __align__(1024) char smem[];
    const int tid = threadIdx.x, warp = tid >> 5, lane = tid & 31;
    const int pair = blockIdx.x >> 2, q = blockIdx.x & 3;
    constexpr int OWN_TILES = CTX / KT - 3 * HELP_TILES;
    const int ntiles = (q == 3) ? OWN_TILES : HELP_TILES;
    const uint32_t sbase = smem_u32(smem);
    unsigned live = warp < W;
    asm volatile("" : "+r"(live));
    const int i = tid & 255;
    uint2* part = &scr->part[pair][0][i];
    unsigned* ready = &scr->ready[pair][0];

    const uint32_t qs = sbase + C::Q_OFF + (warp & (W - 1)) * 512;
    const bool tree = (q == 3) && (warp == 0);
    const size_t goff = (size_t)pair * (CTX * D * 2) + (size_t)(q * HELP_TILES + warp) * TILE_BYTES + lane * 16;
    const char* kp = (const char*)K + goff;
    const char* vp = (const char*)V + goff;
    const uint32_t ring = sbase + warp * C::RING_BYTES;
    const int hi = lane >> 4;
    const uint32_t x0 = hi * 256 + (((lane & 15) ^ hi) << 4);
    uint64_t pol = 0;
    if (EF) asm("createpolicy.fractional.L2::evict_first.b64 %0, 1.0;" : "=l"(pol));
    auto issue = [&](uint32_t slot, const char* src) {
#pragma unroll
        for (int j = 0; j < 8; j++) {
            if (EF) cp16h(slot + j * 512 + (x0 ^ (((2 * j) & 7) << 4)), src + j * 512, pol);
            else cp16(slot + j * 512 + (x0 ^ (((2 * j) & 7) << 4)), src + j * 512);
        }
    };
    constexpr size_t TSTEP = (size_t)W * TILE_BYTES;

    if (warp < W) {
        cp16(qs + lane * 16, (const char*)Q + (size_t)pair * 512 + lane * 16);
        if (q == 3) {
            if (tree) {
                cp16(sbase + C::TR_OFF + lane * 16, (const char*)(lane < 16 ? Kt : Vt) + pair * 256 + (lane & 15) * 16);
                if (lane == 0) cp4(sbase + C::TR_OFF + 512, Mask);
            }
#pragma unroll
            for (int j = 0; j < 3; j++) st_relaxed2_p(part + j * 256, 0u, 0u, 1u);
            bar_arrive(1, W * 32 + 32);
            if (DELAY > 0) { unsigned c0 = gtime32(); while (gtime32() - c0 < (unsigned)DELAY) {} }
        }
#pragma unroll
        for (int s = 0; s < S; s++) {
            issue(ring + s * 2 * TILE_BYTES, kp + s * TSTEP);
            cp_commit();
            issue(ring + s * 2 * TILE_BYTES + TILE_BYTES, vp + s * TSTEP);
            cp_commit();
        }
    } else {
        if (q == 3) {
            bar_sync_p(1, W * 32 + 32, 1u);
            if (lane == 0) asm volatile("fence.acq_rel.gpu;\nst.relaxed.gpu.global.u32 [%0], %1;" :: "l"(ready), "r"(1u) : "memory");
        } else {
            int guard = 0;
            unsigned f;
            do { asm volatile("ld.acquire.gpu.global.u32 %0, [%1];" : "=r"(f) : "l"(ready) : "memory"); } while (f == 0 && ++guard < (1 << 22));
            bar_arrive(0, W * 32 + 32);
        }
        if (!WARM) return;
    }

    const int r7 = lane & 7;
    const uint32_t ka_off = ((lane & 7) + ((lane >> 3) & 1) * 8) * 256 + ((((lane >> 4)) ^ r7) << 4);
    const uint32_t va_off = ((lane & 7) + (lane >> 4) * 8) * 256 + (((((lane >> 3) & 1)) ^ r7) << 4);
    constexpr float SC = 0.08838834764831845f * 1.4426950408889634f;

    float o[8][4];
#pragma unroll
    for (int k = 0; k < 8; k++) { o[k][0] = o[k][1] = o[k][2] = o[k][3] = 0.f; }
    float m0 = -INFINITY, m1 = -INFINITY;
    float ol[4] = {0.f, 0.f, 0.f, 0.f};
    uint32_t qf[8][2];
    const int tend = live ? ntiles : 0;
    if (live) {
        cp_wait<2 * S - 1>();
        __syncwarp();
        const uint32_t qa = qs + (lane & 1) * 256 + (lane >> 3) * 16;
#pragma unroll
        for (int j = 0; j < 4; j++) ldsm4(qf[2 * j][0], qf[2 * j][1], qf[2 * j + 1][0], qf[2 * j + 1][1], qa + j * 64);
        if (tree) {
            float sa[4] = {0.f, 0.f, 0.f, 0.f};
            const uint32_t kt = sbase + C::TR_OFF + (lane >> 4) * 16;
            const uint32_t vt = sbase + C::TR_OFF + 256 + ((lane >> 3) & 1) * 16;
            const uint32_t pb = ((lane & 3) == 0) ? 0x3F80u : 0u;
#pragma unroll
            for (int k = 0; k < 8; k++) {
                uint32_t a0, a1, a2, a3;
                ldsm4(a0, a1, a2, a3, kt + k * 32);
                mma16816(sa, a0, a1, a2, a3, qf[k][0], qf[k][1]);
                ldsm4t(a0, a1, a2, a3, vt + k * 32);
                mma16816(o[k], a0, a1, a2, a3, pb, 0u);
            }
            const uint32_t mw = *(const uint32_t*)(smem + C::TR_OFF + 512);
            const float mk = __uint_as_float(pair >= HKV ? (mw & 0xffff0000u) : (mw << 16));
            const float mb = (1.0f - mk) * (-1000000000.0f);
            m0 = (sa[0] * 0.08838834764831845f + mb) * 1.4426950408889634f;
            m1 = (sa[1] * 0.08838834764831845f + mb) * 1.4426950408889634f;
            ol[0] = ol[1] = 1.0f;
        }
    }

    int slot = 0;
    const char* kn = kp + S * TSTEP;
    const char* vn = vp + S * TSTEP;
#pragma unroll 1
    for (int t = warp; t < tend; t += W) {
        const uint32_t ks = ring + slot * 2 * TILE_BYTES, vs = ks + TILE_BYTES;
        const bool more = (t + S * W) < tend;
        cp_wait<2 * S - 1>();
        __syncwarp();
        float sa[4] = {0.f, 0.f, 0.f, 0.f}, sb[4] = {0.f, 0.f, 0.f, 0.f};
#pragma unroll
        for (int k = 0; k < 8; k += 2) {
            uint32_t a0, a1, a2, a3, b0, b1, b2, b3;
            ldsm4(a0, a1, a2, a3, (ks + ka_off) ^ (k << 5));
            ldsm4(b0, b1, b2, b3, (ks + ka_off) ^ ((k + 1) << 5));
            mma16816(sa, a0, a1, a2, a3, qf[k][0], qf[k][1]);
            mma16816(sb, b0, b1, b2, b3, qf[k + 1][0], qf[k + 1][1]);
        }
        if (more) issue(ks, kn);
        cp_commit();
        kn += TSTEP;
        const float s0 = (sa[0] + sb[0]) * SC, s1 = (sa[1] + sb[1]) * SC, s2 = (sa[2] + sb[2]) * SC, s3 = (sa[3] + sb[3]) * SC;
        float x0m = fmaxf(s0, s2), x1m = fmaxf(s1, s3);
#pragma unroll
        for (int ofs = 4; ofs <= 16; ofs <<= 1) {
            x0m = fmaxf(x0m, __shfl_xor_sync(0xffffffffu, x0m, ofs));
            x1m = fmaxf(x1m, __shfl_xor_sync(0xffffffffu, x1m, ofs));
        }
        const float n0 = fmaxf(m0, x0m), n1 = fmaxf(m1, x1m);
        if (n0 != m0 || n1 != m1) {
            const float al0 = ex2(m0 - n0), al1 = ex2(m1 - n1);
            ol[0] *= al0; ol[1] *= al1;
#pragma unroll
            for (int k = 0; k < 8; k++) { o[k][0] *= al0; o[k][1] *= al1; o[k][2] *= al0; o[k][3] *= al1; }
            m0 = n0; m1 = n1;
        }
        const float p0 = ex2(s0 - m0), p1 = ex2(s1 - m1), p2 = ex2(s2 - m0), p3 = ex2(s3 - m1);
        const uint32_t pb0 = movm_t(pack_bf16(p0, p1)), pb1 = movm_t(pack_bf16(p2, p3));
        mma16816(ol, 0x3F803F80u, 0x3F803F80u, 0x3F803F80u, 0x3F803F80u, pb0, pb1);
        cp_wait<2 * S - 1>();
        __syncwarp();
#pragma unroll
        for (int mt = 0; mt < 8; mt++) {
            uint32_t a0, a1, a2, a3;
            ldsm4t(a0, a1, a2, a3, (vs + va_off) ^ (mt << 5));
            mma16816(o[mt], a0, a1, a2, a3, pb0, pb1);
        }
        if (more) issue(vs, vn);
        cp_commit();
        vn += TSTEP;
        slot = (slot + 1 == S) ? 0 : slot + 1;
    }

    const unsigned poll = live && (q == 3);
    uint2 r[3];
#pragma unroll
    for (int j = 0; j < 3; j++) r[j] = poll ? make_uint2(0, 0) : make_uint2(1, 1);
    if (EARLY) {
#pragma unroll
        for (int j = 0; j < 3; j++) ld_relaxed2_p(r[j], part + j * 256, poll);
    }

    {
        const int g = lane >> 2, tq = lane & 3;
        const uint32_t so = sbase + C::O_OFF + warp * 1024 + g * 16;
#pragma unroll
        for (int mt = 0; mt < 8; mt++) sts4_p(so + mt * 128, o[mt][0], o[mt][1], o[mt][2], o[mt][3], live && (mt >> 1) == tq);
        sts1_p(sbase + C::ML_OFF + ((lane >> 1) * 2 * W + (lane & 1) * W + warp) * 4, (lane & 2) ? ((lane & 1) ? ol[1] : ol[0]) : ((lane & 1) ? m1 : m0), live && lane < 4);
    }
    bar_sync_p(0, (q == 3) ? W * 32 : W * 32 + 32, live);
    const int h = i & 1;
    const float4* mp = (const float4*)(smem + C::ML_OFF + h * W * 4);
    const float4 ma = mp[0], mb = mp[1], la = mp[4], lb = mp[5];
    const float* op = (const float*)(smem + C::O_OFF) + i;
    const float M = fmaxf(fmaxf(fmaxf(ma.x, ma.y), fmaxf(ma.z, ma.w)), fmaxf(fmaxf(mb.x, mb.y), fmaxf(mb.z, mb.w)));
    const float e0 = ex2(ma.x - M), e1 = ex2(ma.y - M), e2 = ex2(ma.z - M), e3 = ex2(ma.w - M);
    const float e4 = ex2(mb.x - M), e5 = ex2(mb.y - M), e6 = ex2(mb.z - M), e7 = ex2(mb.w - M);
    const float acc = ((e0 * op[0] + e1 * op[256]) + (e2 * op[512] + e3 * op[768])) + ((e4 * op[1024] + e5 * op[1280]) + (e6 * op[1536] + e7 * op[1792]));
    const float L = ((e0 * la.x + e1 * la.y) + (e2 * la.z + e3 * la.w)) + ((e4 * lb.x + e5 * lb.y) + (e6 * lb.z + e7 * lb.w));
    if (q != 3) {
        st_relaxed2_p(part + q * 256, enc(acc * rcp(L)), enc(M + lg2(L)), live);
    } else {
        int guard = 0;
        while (true) {
            bool ok = true;
#pragma unroll
            for (int j = 0; j < 3; j++) ok = ok && r[j].x && r[j].y;
            if (ok || ++guard >= (1 << 22)) break;
#pragma unroll
            for (int j = 0; j < 3; j++) ld_relaxed2_p(r[j], part + j * 256, !(r[j].x && r[j].y));
        }
        float Mx = M;
#pragma unroll
        for (int j = 0; j < 3; j++) Mx = fmaxf(Mx, dec(r[j].y));
        const float eo = ex2(M - Mx);
        float num = acc * eo, den = L * eo;
#pragma unroll
        for (int j = 0; j < 3; j++) { const float e = ex2(dec(r[j].y) - Mx); num += e * dec(r[j].x); den += e; }
        const __nv_bfloat16 res = __float2bfloat16(num * rcp(den));
        const int dim = (i >> 5) * 16 + ((i >> 1) & 1) * 8 + ((i >> 2) & 7);
        st_b16_p(Out + pair * 256 + h * 128 + dim, __bfloat16_as_ushort(res), live);
        st_relaxed1_p(ready, 0u, live && tid == 0);
    }
}

template<int S, int HELP_TILES, int WARM, int PROF, int EARLY, int DELAY, int EF>
inline void launch(const void* Q, const void* K, const void* V, const void* Kt, const void* Vt, const void* Mask, void* Out, cudaStream_t s) {
    auto kern = attn_kernel<S, HELP_TILES, WARM, PROF, EARLY, DELAY, EF>;
    static bool init = false;
    static Scratch* gp = nullptr;
    if (!init) { cudaFuncSetAttribute(kern, cudaFuncAttributeMaxDynamicSharedMemorySize, Cfg<S>::SMEM); cudaGetSymbolAddress((void**)&gp, g_scr); init = true; }
    kern<<<NPAIR * CPP, W * 32 + 32, Cfg<S>::SMEM, s>>>((const __nv_bfloat16*)Q, (const __nv_bfloat16*)K, (const __nv_bfloat16*)V,
        (const __nv_bfloat16*)Kt, (const __nv_bfloat16*)Vt, (const __nv_bfloat16*)Mask, (__nv_bfloat16*)Out, gp);
}
}

extern "C" void kernel_launch(void* const* d_in, const int* in_sizes, int n_in, void* d_out, int out_size) {
    (void)in_sizes; (void)n_in; (void)out_size;
    launch<2, 64, 0, 0, 1, 0, 1>(d_in[0], d_in[1], d_in[2], d_in[3], d_in[4], d_in[5], d_out, cudaStreamPerThread);
}
```

```cpp
#include <cuda_runtime.h>
#include <cuda_bf16.h>
#include <stdint.h>

namespace {

constexpr int B_ = 2, HKV = 16, CTX = 4096, D = 128;
constexpr int NPAIR = B_ * HKV;
constexpr int CPP = 4;
constexpr int KT = 16;
constexpr int TILE_BYTES = KT * D * 2;
constexpr int W = 4;
constexpr int NT = CTX / KT / CPP / W;
constexpr int R = 6;
constexpr int THREADS = W * 32 + 32;

constexpr int RING_BYTES = R * TILE_BYTES;
constexpr int Q_OFF = W * RING_BYTES;
constexpr int O_STRIDE = 2 * 144 * 4;
constexpr int O_OFF = Q_OFF + W * 512;
constexpr int ML_OFF = O_OFF + W * O_STRIDE;
constexpr int MQ_OFF = ML_OFF + 128;
constexpr int T_OFF = MQ_OFF + 16;
constexpr int SMEM_BYTES = T_OFF + 1024;
constexpr int NP = NT - R;
constexpr int JP = 6;

struct Scratch { uint2 slot[NPAIR][CPP][16]; };
__device__ Scratch g_scr;

__device__ __forceinline__ uint32_t smem_u32(const void* p) { return (uint32_t)__cvta_generic_to_shared(p); }
__device__ __forceinline__ void cp16(uint32_t dst, const void* src) {
    asm volatile("cp.async.cg.shared.global [%0], [%1], 16;" :: "r"(dst), "l"(src) : "memory");
}
__device__ __forceinline__ void cp16_stream(uint32_t dst, const void* src) {
    asm volatile("{\n.reg .b64 p;\nmov.b64 p, 0x12F0000000000000;\ncp.async.cg.shared.global.L2::cache_hint [%0], [%1], 16, p;\n}"
                 :: "r"(dst), "l"(src) : "memory");
}
__device__ __forceinline__ void cp_commit() { asm volatile("cp.async.commit_group;" ::: "memory"); }
template<int N> __device__ __forceinline__ void cp_wait() { asm volatile("cp.async.wait_group %0;" :: "n"(N) : "memory"); }
__device__ __forceinline__ void cp_wait_n(int n) {
    if (n >= 5) cp_wait<5>(); else if (n == 4) cp_wait<4>(); else if (n == 3) cp_wait<3>();
    else if (n == 2) cp_wait<2>(); else if (n == 1) cp_wait<1>(); else cp_wait<0>();
}
__device__ __forceinline__ void ldsm4(uint32_t& r0, uint32_t& r1, uint32_t& r2, uint32_t& r3, uint32_t a) {
    asm volatile("ldmatrix.sync.aligned.m8n8.x4.shared.b16 {%0,%1,%2,%3}, [%4];" : "=r"(r0), "=r"(r1), "=r"(r2), "=r"(r3) : "r"(a) : "memory");
}
__device__ __forceinline__ void ldsm4t(uint32_t& r0, uint32_t& r1, uint32_t& r2, uint32_t& r3, uint32_t a) {
    asm volatile("ldmatrix.sync.aligned.m8n8.x4.trans.shared.b16 {%0,%1,%2,%3}, [%4];" : "=r"(r0), "=r"(r1), "=r"(r2), "=r"(r3) : "r"(a) : "memory");
}
__device__ __forceinline__ void mma16816(float (&c)[4], uint32_t a0, uint32_t a1, uint32_t a2, uint32_t a3, uint32_t b0, uint32_t b1) {
    asm volatile("mma.sync.aligned.m16n8k16.row.col.f32.bf16.bf16.f32 {%0,%1,%2,%3}, {%4,%5,%6,%7}, {%8,%9}, {%0,%1,%2,%3};"
        : "+f"(c[0]), "+f"(c[1]), "+f"(c[2]), "+f"(c[3]) : "r"(a0), "r"(a1), "r"(a2), "r"(a3), "r"(b0), "r"(b1));
}
__device__ __forceinline__ uint32_t movm_t(uint32_t a) { uint32_t d; asm volatile("movmatrix.sync.aligned.m8n8.trans.b16 %0, %1;" : "=r"(d) : "r"(a)); return d; }
__device__ __forceinline__ uint32_t pack_bf16(float lo, float hi) { uint32_t d; asm("cvt.rn.bf16x2.f32 %0, %1, %2;" : "=r"(d) : "f"(hi), "f"(lo)); return d; }
__device__ __forceinline__ float ex2(float x) { float y; asm("ex2.approx.ftz.f32 %0, %1;" : "=f"(y) : "f"(x)); return y; }
__device__ __forceinline__ float rcp(float x) { float y; asm("rcp.approx.ftz.f32 %0, %1;" : "=f"(y) : "f"(x)); return y; }
__device__ __forceinline__ unsigned enc(float x) { unsigned b = __float_as_uint(x); b = (b == 0xFFFFFFFFu) ? 0x7FFFFFFFu : b; return ~b; }
__device__ __forceinline__ float dec(unsigned u) { return __uint_as_float(~u); }
__device__ __forceinline__ float bf_lo(uint32_t x) { return __uint_as_float(x << 16); }
__device__ __forceinline__ float bf_hi(uint32_t x) { return __uint_as_float(x & 0xffff0000u); }
__device__ __forceinline__ void ld_rec_p(uint2& v, const uint2* p, unsigned pred) {
    asm volatile("{\n.reg .pred p;\nsetp.ne.u32 p, %3, 0;\n@p ld.acquire.gpu.global.v2.u32 {%0,%1}, [%2];\n}" : "+r"(v.x), "+r"(v.y) : "l"(p), "r"(pred) : "memory");
}
__device__ __forceinline__ void st_rec_p(uint2* p, unsigned a, unsigned b, unsigned pred) {
    asm volatile("{\n.reg .pred p;\nsetp.ne.u32 p, %3, 0;\n@p st.relaxed.gpu.global.v2.u32 [%0], {%1,%2};\n}" :: "l"(p), "r"(a), "r"(b), "r"(pred) : "memory");
}
__device__ __forceinline__ void sts1_p(uint32_t a, float x, unsigned pred) {
    asm volatile("{\n.reg .pred p;\nsetp.ne.u32 p, %2, 0;\n@p st.shared.f32 [%0], %1;\n}" :: "r"(a), "f"(x), "r"(pred) : "memory");
}
__device__ __forceinline__ void bar_sync(int id, unsigned count) { asm volatile("barrier.cta.sync.aligned %0, %1;" :: "r"(id), "r"(count) : "memory"); }
__device__ __forceinline__ void bar_arrive(int id, unsigned count) { asm volatile("barrier.cta.arrive.aligned %0, %1;" :: "r"(id), "r"(count) : "memory"); }

__global__ void __launch_bounds__(THREADS, 1)
attn_kernel(const __nv_bfloat16* __restrict__ Q, const __nv_bfloat16* __restrict__ K, const __nv_bfloat16* __restrict__ V,
            const __nv_bfloat16* __restrict__ Kt, const __nv_bfloat16* __restrict__ Vt, const __nv_bfloat16* __restrict__ Mask,
            __nv_bfloat16* __restrict__ Out, Scratch* __restrict__ scr)
{
    extern __shared__ __align__(1024) char smem[];
    const int tid = threadIdx.x, warp = tid >> 5, lane = tid & 31;
    const int pair = blockIdx.x >> 2, q = blockIdx.x & 3;
    const uint32_t sbase = smem_u32(smem);
    constexpr float SCALE = 0.08838834764831845f;
    constexpr float LOG2E = 1.4426950408889634f;
    constexpr float SC = SCALE * LOG2E;

    if (warp == W) {
        float mt0 = -INFINITY, mt1 = -INFINITY;
        uint32_t vA = 0, vB = 0;
        if (q == 3) {
            const uint2 q0 = *(const uint2*)((const char*)Q + pair * 512 + lane * 8);
            const uint2 q1 = *(const uint2*)((const char*)Q + pair * 512 + 256 + lane * 8);
            const uint2 kt = *(const uint2*)((const char*)Kt + pair * 256 + lane * 8);
            const uint2 vv = *(const uint2*)((const char*)Vt + pair * 256 + lane * 8);
            vA = vv.x; vB = vv.y;
            const unsigned short mk = *(const unsigned short*)(Mask + (pair >> 4));
            asm volatile("st.global.v4.u32 [%0], {%1,%1,%1,%1};" :: "l"((char*)Out + pair * 512 + lane * 16), "r"(0u) : "memory");
            __syncwarp();
            asm volatile("fence.acq_rel.gpu;" ::: "memory");
            float s0 = (bf_lo(q0.x) * bf_lo(kt.x) + bf_hi(q0.x) * bf_hi(kt.x)) + (bf_lo(q0.y) * bf_lo(kt.y) + bf_hi(q0.y) * bf_hi(kt.y));
            float s1 = (bf_lo(q1.x) * bf_lo(kt.x) + bf_hi(q1.x) * bf_hi(kt.x)) + (bf_lo(q1.y) * bf_lo(kt.y) + bf_hi(q1.y) * bf_hi(kt.y));
#pragma unroll
            for (int ofs = 1; ofs <= 16; ofs <<= 1) { s0 += __shfl_xor_sync(0xffffffffu, s0, ofs); s1 += __shfl_xor_sync(0xffffffffu, s1, ofs); }
            const float mb = (1.0f - __uint_as_float((uint32_t)mk << 16)) * (-1000000000.0f);
            mt0 = (s0 * SCALE + mb) * LOG2E;
            mt1 = (s1 * SCALE + mb) * LOG2E;
        }
        bar_sync(2, THREADS);
        const int h = (lane >> 3) & 1, w = lane & 7;
        const float* ml = (const float*)(smem + ML_OFF);
        const float m = (w < W) ? ml[h * W + w] : -INFINITY, l = (w < W) ? ml[2 * W + h * W + w] : 0.f;
        const float mt = h ? mt1 : mt0;
        float M = fmaxf(m, mt);
#pragma unroll
        for (int ofs = 1; ofs <= 4; ofs <<= 1) M = fmaxf(M, __shfl_xor_sync(0xffffffffu, M, ofs));
        float L = ex2(m - M) * l;
#pragma unroll
        for (int ofs = 1; ofs <= 4; ofs <<= 1) L += __shfl_xor_sync(0xffffffffu, L, ofs);
        const float et = ex2(mt - M);
        L += et;
        if (lane < 16 && w == 0) ((float*)(smem + MQ_OFF))[h] = M;
        {
            const float f0 = __shfl_sync(0xffffffffu, et, 0), f1 = __shfl_sync(0xffffffffu, et, 8);
            float4* T = (float4*)(smem + T_OFF) + lane;
            T[0] = make_float4(f0 * bf_lo(vA), f0 * bf_hi(vA), f0 * bf_lo(vB), f0 * bf_hi(vB));
            T[32] = make_float4(f1 * bf_lo(vA), f1 * bf_hi(vA), f1 * bf_lo(vB), f1 * bf_hi(vB));
        }
#pragma unroll
        for (int k = 0; k < W; k++) bar_arrive(3 + k, 64);
        const bool xch = lane < 16 && w < CPP && w != q;
        st_rec_p(&scr->slot[pair][w & 3][q * 2 + h], enc(M), enc(L), xch);
        uint2* mine = &scr->slot[pair][q][(w & 3) * 2 + h];
        uint2 r = make_uint2(0, 0);
        bar_sync(1, THREADS);
        int guard = 0;
        do {
            ld_rec_p(r, mine, xch && !(r.x && r.y));
        } while (!__all_sync(0xffffffffu, !xch || (r.x && r.y)) && ++guard < (1 << 22));
        st_rec_p(mine, 0u, 0u, xch);
        const float Mj = xch ? dec(r.x) : (w == q ? M : -INFINITY);
        const float Lj = xch ? dec(r.y) : (w == q ? L : 0.f);
        float Mg = Mj;
#pragma unroll
        for (int ofs = 1; ofs <= 2; ofs <<= 1) Mg = fmaxf(Mg, __shfl_xor_sync(0xffffffffu, Mg, ofs));
        float Lg = ex2(Mj - Mg) * Lj;
#pragma unroll
        for (int ofs = 1; ofs <= 2; ofs <<= 1) Lg += __shfl_xor_sync(0xffffffffu, Lg, ofs);
        Mg = __shfl_sync(0xffffffffu, Mg, lane & 8);
        Lg = __shfl_sync(0xffffffffu, Lg, lane & 8);
        if (lane < 16 && w == 0) ((float*)(smem + MQ_OFF))[2 + h] = ex2(M - Mg) * rcp(Lg);
        bar_arrive(0, THREADS);
        return;
    }

    const uint32_t qs = sbase + Q_OFF + warp * 512;
    const size_t goff = (size_t)pair * (CTX * D * 2) + (size_t)(q * (NT * W) + warp) * TILE_BYTES + lane * 16;
    const char* kp = (const char*)K + goff;
    const char* vp = (const char*)V + goff;
    const uint32_t ring = sbase + warp * RING_BYTES;
    const int hi = lane >> 4;
    const uint32_t x0 = hi * 256 + (((lane & 15) ^ hi) << 4);
    uint32_t dst[4];
#pragma unroll
    for (int j = 0; j < 4; j++) dst[j] = ring + (x0 ^ (j << 5));
    constexpr size_t TSTEP = (size_t)W * TILE_BYTES;
    auto issue = [&](int u) {
        const char* src = (u < NT) ? kp + (size_t)u * TSTEP : vp + (size_t)(u - NT) * TSTEP;
        const int so = (u % R) * TILE_BYTES;
#pragma unroll
        for (int j = 0; j < 8; j++) cp16_stream(dst[j & 3] + so + j * 512, src + j * 512);
        cp_commit();
    };

    cp16(qs + lane * 16, (const char*)Q + (size_t)pair * 512 + lane * 16);
#pragma unroll
    for (int u = 0; u < R; u++) issue(u);

    const int r7 = lane & 7;
    const uint32_t ka0 = ring + (r7 + ((lane >> 3) & 1) * 8) * 256 + (((lane >> 4) ^ r7) << 4);
    const uint32_t va0 = ring + (r7 + (lane >> 4) * 8) * 256 + ((((lane >> 3) & 1) ^ r7) << 4);
    uint32_t ka[4], va[4];
#pragma unroll
    for (int k = 0; k < 4; k++) { ka[k] = ka0 ^ (k << 5); va[k] = va0 ^ (k << 5); }

    uint32_t qf[8][2];
    float s[NT][2];
#pragma unroll
    for (int j = 0; j < NT; j++) {
        cp_wait<R - 1>();
        __syncwarp();
        if (j == 0) {
            const uint32_t qa = qs + ((lane >> 1) & 1) * 256 + (lane >> 3) * 16;
#pragma unroll
            for (int k = 0; k < 4; k++) ldsm4(qf[2 * k][0], qf[2 * k][1], qf[2 * k + 1][0], qf[2 * k + 1][1], qa + k * 64);
        }
        const int so = (j % R) * TILE_BYTES;
        float sa[4] = {0.f, 0.f, 0.f, 0.f}, sb[4] = {0.f, 0.f, 0.f, 0.f};
#pragma unroll
        for (int k = 0; k < 8; k += 2) {
            uint32_t a0, a1, a2, a3, b0, b1, b2, b3;
            ldsm4(a0, a1, a2, a3, ka[k & 3] + so + (k >> 2) * 128);
            ldsm4(b0, b1, b2, b3, ka[(k + 1) & 3] + so + (k >> 2) * 128);
            mma16816(sa, a0, a1, a2, a3, qf[k][0], qf[k][1]);
            mma16816(sb, b0, b1, b2, b3, qf[k + 1][0], qf[k + 1][1]);
        }
        issue(j + R);
        s[j][0] = sa[0] + sb[0]; s[j][1] = sa[2] + sb[2];
    }

    uint32_t pb[NT][2];
    float m;
    {
        float xm = fmaxf(s[0][0], s[0][1]);
#pragma unroll
        for (int j = 1; j < NT; j++) xm = fmaxf(xm, fmaxf(s[j][0], s[j][1]));
#pragma unroll
        for (int ofs = 4; ofs <= 16; ofs <<= 1) xm = fmaxf(xm, __shfl_xor_sync(0xffffffffu, xm, ofs));
        m = xm * SC;
        float l = 0.f;
#pragma unroll
        for (int j = 0; j < NT; j++) {
            const float p0 = ex2(fmaf(s[j][0], SC, -m)), p1 = ex2(fmaf(s[j][1], SC, -m));
            l += p0 + p1;
            if (j < NP) { pb[j][0] = movm_t(pack_bf16(p0, p0)); pb[j][1] = movm_t(pack_bf16(p1, p1)); }
        }
#pragma unroll
        for (int ofs = 4; ofs <= 16; ofs <<= 1) l += __shfl_xor_sync(0xffffffffu, l, ofs);
        sts1_p(sbase + ML_OFF + ((lane >> 1) * 2 * W + (lane & 1) * W + warp) * 4, (lane & 2) ? l : m, lane < 4);
        bar_arrive(2, THREADS);
    }

    const int i = tid;
    const int h = i & 1;
    float tv0 = 0.f, tv1 = 0.f;
    const unsigned never = (Out == nullptr);
    const uint32_t dep = sbase + O_OFF + warp * O_STRIDE + ((lane & 1) * 144 + (lane >> 2) + (lane & 2) * 4) * 4;
    const uint32_t fin_op = sbase + O_OFF + (((i >> 6) & 1) * 144 + (i & 63) * 2) * 4, fin_gs = sbase + MQ_OFF + 8 + ((i >> 6) & 1) * 4;
    const char* fin_out = (const char*)Out + pair * 512 + (i & 127) * 4;

    float o[8][4];
#pragma unroll
    for (int k = 0; k < 8; k++) { o[k][0] = o[k][1] = o[k][2] = o[k][3] = 0.f; }
#pragma unroll
    for (int j = 0; j < NT; j++) {
        const int u = NT + j;
        if (j == NP) {
            bar_sync(3 + warp, 64);
            const float mq = *(const float*)(smem + MQ_OFF + h * 4);
            { const float2 t2 = *(const float2*)(smem + T_OFF + (i & 127) * 8); tv0 = t2.x; tv1 = t2.y; }
            const float f = ex2(m - mq);
#pragma unroll
            for (int k = 0; k < 8; k++) { o[k][0] *= f; o[k][2] *= f; }
#pragma unroll
            for (int jj = NP; jj < NT; jj++) {
                const float p0 = ex2(fmaf(s[jj][0], SC, -mq)), p1 = ex2(fmaf(s[jj][1], SC, -mq));
                pb[jj][0] = movm_t(pack_bf16(p0, p0)); pb[jj][1] = movm_t(pack_bf16(p1, p1));
            }
        }
        if (j == NT - 1) {
            sts1_p(sbase, __uint_as_float(pb[j][0]), never); sts1_p(sbase, __uint_as_float(pb[j][1]), never);
        }
        cp_wait_n(2 * NT - 1 - u < R - 1 ? 2 * NT - 1 - u : R - 1);
        __syncwarp();
        if (j == JP) bar_arrive(1, THREADS);
        const int so = (u % R) * TILE_BYTES;
#pragma unroll
        for (int mt = 0; mt < 8; mt++) {
            uint32_t a0, a1, a2, a3;
            ldsm4t(a0, a1, a2, a3, va[mt & 3] + so + (mt >> 2) * 128);
            mma16816(o[mt], a0, a1, a2, a3, pb[j][0], pb[j][1]);
        }
        if (u + R < 2 * NT) issue(u + R);
    }
    static_assert(R == 6 && W == 4, "wait chain and final combine are written for W == 4, R == 6");

#pragma unroll
    for (int mt = 0; mt < 8; mt++)
        asm volatile("st.shared.f32 [%0], %1;" :: "r"(dep + mt * 64), "f"((lane & 2) ? o[mt][2] : o[mt][0]) : "memory");
    bar_sync(0, THREADS);
    float2 pv[W]; float gs;
#pragma unroll
    for (int k = 0; k < W; k++) asm volatile("ld.shared.v2.f32 {%0,%1}, [%2];" : "=f"(pv[k].x), "=f"(pv[k].y) : "r"(fin_op + k * O_STRIDE) : "memory");
    asm volatile("ld.shared.f32 %0, [%1];" : "=f"(gs) : "r"(fin_gs) : "memory");
    const float v0 = (tv0 + pv[0].x) + (pv[1].x + (pv[2].x + pv[3].x));
    const float v1 = (tv1 + pv[0].y) + (pv[1].y + (pv[2].y + pv[3].y));
    asm volatile("red.relaxed.gpu.global.add.noftz.bf16x2 [%0], %1;" :: "l"(fin_out), "r"(pack_bf16(v0 * gs, v1 * gs)) : "memory");
}

}

extern "C" void kernel_launch(void* const* d_in, const int* in_sizes, int n_in, void* d_out, int out_size) {
    (void)in_sizes; (void)n_in; (void)out_size;
    static Scratch* scratch = nullptr;
    if (!scratch) {
        cudaFuncSetAttribute(attn_kernel, cudaFuncAttributeMaxDynamicSharedMemorySize, SMEM_BYTES);
        cudaGetSymbolAddress((void**)&scratch, g_scr);
    }
    attn_kernel<<<NPAIR * CPP, THREADS, SMEM_BYTES, cudaStreamPerThread>>>(
        (const __nv_bfloat16*)d_in[0], (const __nv_bfloat16*)d_in[1], (const __nv_bfloat16*)d_in[2],
        (const __nv_bfloat16*)d_in[3], (const __nv_bfloat16*)d_in[4], (const __nv_bfloat16*)d_in[5],
        (__nv_bfloat16*)d_out, scratch);
}
```
